```python
import torch

def _softmax(x, axis=-1):
    return torch.softmax(x, dim=axis)
def _gelu(x):
    return torch.nn.functional.gelu(x, approximate="tanh")
def _silu(x):
    return torch.nn.functional.silu(x)
def _sigmoid(x):
    return torch.sigmoid(x)
def _layernorm(x, axis=-1, eps=1e-5):
    m = x.mean(dim=axis, keepdim=True)
    v = x.var(dim=axis, keepdim=True, unbiased=False)
    return (x - m) / torch.sqrt(v + eps)
def _scatter_add(tgt, idx, src, axis=0):
    return tgt.clone().index_add_(axis, idx, src)
def _segment_sum(src, seg, n):
    out = torch.zeros((n,) + src.shape[1:], dtype=src.dtype)
    return out.index_add_(0, seg, src)
def _pad(x, pw):
    flat = tuple(v for pair in reversed(pw) for v in pair)
    return torch.nn.functional.pad(x, flat)

kernel_name = 'concat_heads__softmax_full_mha__compressed_kv_cla__prompt'

def setup_inputs():

    _w = (lambda a: (lambda t: t.to(torch.bfloat16) if t.is_floating_point() else t)(torch.as_tensor(a)))
    def _A_setup():
        B, S, D = 1, 2048, 448
        return {
            "x": _w((lambda *s: torch.randn(*s, dtype=torch.bfloat16) * 0.4)(B, S, D)),
            "wqkv": _w((lambda *s: torch.randn(*s, dtype=torch.bfloat16) * 0.4)(D, 3 * D)),
            "wo": _w((lambda *s: torch.randn(*s, dtype=torch.bfloat16) * 0.05)(D, D)),
        }
    _A_in = _A_setup()

    def _B_setup():
        B, H, Sq, Sk, D, M = 1, 16, 2048, 2048, 256, 448
        Dc = 4 * D
        return {
            "x": _w((lambda *s: torch.randn(*s, dtype=torch.bfloat16) * 0.2)(B, Sq, M)),
            "c_kv": _w((lambda *s: torch.randn(*s, dtype=torch.bfloat16) * 1.6)(B, Sk, Dc)),
            "w_q": _w((lambda *s: torch.randn(*s, dtype=torch.bfloat16) * 3.2)(M, H, D) * (M ** -0.5)),
            "w_uk": _w((lambda *s: torch.randn(*s, dtype=torch.bfloat16) * 3.2)(Dc, H, D) * (Dc ** -0.5)),
            "w_uv": _w((lambda *s: torch.randn(*s, dtype=torch.bfloat16) * 1.6)(Dc, H, D) * (Dc ** -0.5)),
            "w_o": _w((lambda *s: torch.randn(*s, dtype=torch.bfloat16) * 1.6)(H, D, M) * ((H * D) ** -0.5)),
        }
    _B_in = _B_setup()

    return {
        "A_x": _A_in["x"],
        "A_wqkv": _A_in["wqkv"],
        "A_wo": _A_in["wo"],
        "B_x": _B_in["x"],
        "B_c_kv": _B_in["c_kv"],
        "B_w_q": _B_in["w_q"],
        "B_w_uk": _B_in["w_uk"],
        "B_w_uv": _B_in["w_uv"],
        "B_w_o": _B_in["w_o"],
    }

def reference(A_x, A_wqkv, A_wo, B_x, B_c_kv, B_w_q, B_w_uk, B_w_uv, B_w_o):
    def _A_ref(x, wqkv, wo):
        B, S, D = x.shape
        H = 16; Dh = D // H
        qkv = (lambda x, *d: x.permute(*d))((x @ wqkv).reshape(B, S, 3, H, Dh), 2, 0, 3, 1, 4)
        q, k, v = qkv[0], qkv[1], qkv[2]
        scale = Dh ** -0.5
        scores = torch.einsum("bhqd,bhkd->bhqk", q, k) * scale
        p = _softmax(scores, axis=-1)
        o = torch.einsum("bhqk,bhkd->bhqd", p, v)
        return (lambda x, *d: x.permute(*d))(o, 0, 2, 1, 3).reshape(B, S, D) @ wo

    def _B_ref(x, c_kv, w_q, w_uk, w_uv, w_o):
        B, Sq, M = x.shape[0], x.shape[1], x.shape[2]
        Sk = c_kv.shape[1]
        H, D = w_q.shape[1], w_q.shape[2]
        q = torch.einsum("bqm,mhd->bhqd", x, w_q)
        k = torch.einsum("bkc,chd->bhkd", c_kv, w_uk)
        v = torch.einsum("bkc,chd->bhkd", c_kv, w_uv)
        scores = torch.einsum("bhqd,bhkd->bhqk", q, k) * (D ** -0.5)
        off = Sk - Sq
        qi = torch.arange(Sq)[:, None]
        kj = torch.arange(Sk)[None, :]
        cmask = kj <= (qi + off)
        scores = torch.where(cmask[None, None], scores, -1e9)
        p = _softmax(scores, axis=-1)
        ctx = torch.einsum("bhqk,bhkd->bhqd", p, v)
        return torch.einsum("bhqd,hdm->bqm", ctx, w_o)

    a = _A_ref(A_x, A_wqkv, A_wo)
    b = _B_ref(B_x, B_c_kv, B_w_q, B_w_uk, B_w_uv, B_w_o)
    return torch.concatenate([a, b], axis=-1)
```

```cpp
#include <cuda_runtime.h>
#include <cuda_bf16.h>
#include <cuda.h>
#include <stdint.h>

namespace {

constexpr int SEQ = 2048;
constexpr int DM = 448;
constexpr int NH = 16;
constexpr int DC = 1024;
constexpr int OUTW = 896;

__device__ __align__(1024) uint8_t g_K[NH * 32 * 32768];
__device__ __align__(1024) uint8_t g_V[NH * 32 * 32768];
__device__ __align__(1024) uint8_t g_QA[NH * 32 * 4096];
__device__ __align__(1024) uint8_t g_KVA[NH * 33 * 8192];
__device__ __align__(1024) __nv_bfloat16 g_oA[SEQ * DM];

__device__ __forceinline__ uint32_t smem_u32(const void* p) { return (uint32_t)__cvta_generic_to_shared(p); }
__device__ __forceinline__ void wgmma_fence() { asm volatile("wgmma.fence.sync.aligned;" ::: "memory"); }
__device__ __forceinline__ void wgmma_commit() { asm volatile("wgmma.commit_group.sync.aligned;" ::: "memory"); }
template <int N> __device__ __forceinline__ void wgmma_wait() { asm volatile("wgmma.wait_group.sync.aligned %0;" ::"n"(N) : "memory"); }
template <int N> __device__ __forceinline__ void fence_regs(float (&d)[N]) {
#pragma unroll
  for (int i = 0; i < N; i++) asm volatile("" : "+f"(d[i])::"memory");
}
template <int N> __device__ __forceinline__ void fence_regs(uint32_t (&d)[N]) {
#pragma unroll
  for (int i = 0; i < N; i++) asm volatile("" : "+r"(d[i])::"memory");
}
__device__ __forceinline__ uint32_t desc_kmajor(uint32_t addr) { return ((addr & 0x3FFFFu) >> 4) | (1u << 16); }
__device__ __forceinline__ uint32_t desc_nmajor128(uint32_t addr) { return ((addr & 0x3FFFFu) >> 4) | (512u << 16); }

__device__ __forceinline__ void mbar_init(uint32_t bar, uint32_t count) {
  asm volatile("mbarrier.init.shared::cta.b64 [%0], %1;" ::"r"(bar), "r"(count) : "memory");
}
__device__ __forceinline__ void mbar_expect_tx(uint32_t bar, uint32_t bytes) {
  asm volatile("mbarrier.arrive.expect_tx.shared::cta.b64 _, [%0], %1;" ::"r"(bar), "r"(bytes) : "memory");
}
__device__ __forceinline__ void mbar_arrive(uint32_t bar) {
  asm volatile("mbarrier.arrive.shared::cta.b64 _, [%0];" ::"r"(bar) : "memory");
}
__device__ __forceinline__ void mbar_arrive_cta(uint32_t bar, uint32_t cta) {
  asm volatile("{\n.reg .b32 ra;\nmapa.shared::cluster.u32 ra, %0, %1;\nmbarrier.arrive.shared::cluster.b64 _, [ra];\n}\n" ::"r"(bar), "r"(cta) : "memory");
}
__device__ __forceinline__ void mbar_wait(uint32_t bar, uint32_t parity) {
  asm volatile("{\n.reg .pred p;\n.reg .u32 n;\nmov.u32 n, 0;\n"
               "LAB_WAIT:\n"
               "mbarrier.try_wait.parity.shared::cta.b64 p, [%0], %1;\n"
               "@p bra LAB_DONE;\n"
               "add.u32 n, n, 1;\n"
               "setp.lt.u32 p, n, 8388608;\n"
               "@p bra LAB_WAIT;\n"
               "trap;\n"
               "LAB_DONE:\n}\n" ::"r"(bar), "r"(parity) : "memory");
}
__device__ __forceinline__ void fence_async_smem() { asm volatile("fence.proxy.async.shared::cta;" ::: "memory"); }
__device__ __forceinline__ void bar_sync(int id, int n) { asm volatile("bar.sync %0, %1;" ::"r"(id), "r"(n) : "memory"); }
__device__ __forceinline__ void bar_arrive(int id, int n) { asm volatile("bar.arrive %0, %1;" ::"r"(id), "r"(n) : "memory"); }
__device__ __forceinline__ void cluster_sync() {
  asm volatile("barrier.cluster.arrive.relaxed;\nbarrier.cluster.wait;" ::: "memory");
}
template <int N> __device__ __forceinline__ void reg_inc() { asm volatile("setmaxnreg.inc.sync.aligned.u32 %0;" ::"n"(N)); }
template <int N> __device__ __forceinline__ void reg_dec() { asm volatile("setmaxnreg.dec.sync.aligned.u32 %0;" ::"n"(N)); }

__device__ __forceinline__ void tma2d(uint32_t dst, const CUtensorMap* tm, int c0, int c1, uint32_t bar) {
  asm volatile("cp.async.bulk.tensor.2d.shared::cluster.global.mbarrier::complete_tx::bytes [%0], [%1, {%3, %4}], [%2];"
               ::"r"(dst), "l"(tm), "r"(bar), "r"(c0), "r"(c1) : "memory");
}
__device__ __forceinline__ void tma2d_mc(uint32_t dst, const CUtensorMap* tm, int c0, int c1, uint32_t bar) {
  asm volatile("cp.async.bulk.tensor.2d.shared::cluster.global.mbarrier::complete_tx::bytes.multicast::cluster [%0], [%1, {%3, %4}], [%2], %5;"
               ::"r"(dst), "l"(tm), "r"(bar), "r"(c0), "r"(c1), "h"((uint16_t)3) : "memory");
}
__device__ __forceinline__ void tma3d_mc(uint32_t dst, const CUtensorMap* tm, int c0, int c1, int c2, uint32_t bar) {
  asm volatile("cp.async.bulk.tensor.3d.shared::cluster.global.mbarrier::complete_tx::bytes.multicast::cluster [%0], [%1, {%3, %4, %5}], [%2], %6;"
               ::"r"(dst), "l"(tm), "r"(bar), "r"(c0), "r"(c1), "r"(c2), "h"((uint16_t)3) : "memory");
}
__device__ __forceinline__ void bulk_load(uint32_t dst, const void* src, uint32_t bytes, uint32_t bar) {
  asm volatile("cp.async.bulk.shared::cluster.global.mbarrier::complete_tx::bytes [%0], [%1], %2, [%3];"
               ::"r"(dst), "l"(src), "r"(bytes), "r"(bar) : "memory");
}
__device__ __forceinline__ void bulk_load_mc(uint32_t dst, const void* src, uint32_t bytes, uint32_t bar) {
  asm volatile("cp.async.bulk.shared::cluster.global.mbarrier::complete_tx::bytes.multicast::cluster [%0], [%1], %2, [%3], %4;"
               ::"r"(dst), "l"(src), "r"(bytes), "r"(bar), "h"((uint16_t)3) : "memory");
}
__device__ __forceinline__ void bulk_store(void* dst, uint32_t src, uint32_t bytes) {
  asm volatile("cp.async.bulk.global.shared::cta.bulk_group [%0], [%1], %2;" ::"l"(dst), "r"(src), "r"(bytes) : "memory");
}
__device__ __forceinline__ void bulk_commit() { asm volatile("cp.async.bulk.commit_group;" ::: "memory"); }
__device__ __forceinline__ void bulk_wait_read() { asm volatile("cp.async.bulk.wait_group.read 0;" ::: "memory"); }
__device__ __forceinline__ void bulk_wait_all() { asm volatile("cp.async.bulk.wait_group 0;" ::: "memory"); }

__device__ __forceinline__ uint32_t pack_bf16(float lo, float hi) {
  uint32_t r;
  asm("cvt.rn.bf16x2.f32 %0, %1, %2;" : "=r"(r) : "f"(hi), "f"(lo));
  return r;
}
__device__ __forceinline__ void stmatrix_x4(uint32_t addr, uint32_t r0, uint32_t r1, uint32_t r2, uint32_t r3) {
  asm volatile("stmatrix.sync.aligned.m8n8.x4.shared.b16 [%0], {%1, %2, %3, %4};" ::"r"(addr), "r"(r0), "r"(r1), "r"(r2), "r"(r3) : "memory");
}
__device__ __forceinline__ float ex2(float x) {
  float y;
  asm("ex2.approx.ftz.f32 %0, %1;" : "=f"(y) : "f"(x));
  return y;
}

__device__ __forceinline__ float rcp(float x) {
  float y;
  asm("rcp.approx.ftz.f32 %0, %1;" : "=f"(y) : "f"(x));
  return y;
}

__device__ __forceinline__ void wgmma_ss_n256_t1(float (&d)[128], uint32_t da, uint32_t db, int scale_d) {
  asm volatile("{\n.reg .pred p;\n.reg .b32 hi;\n.reg .b64 da, db;\nsetp.ne.b32 p, %130, 0;\nmov.b32 hi, 0x40000040;\nmov.b64 da, {%128, hi};\nmov.b64 db, {%129, hi};\n"
    "wgmma.mma_async.sync.aligned.m64n256k16.f32.bf16.bf16 {"
    "%0,%1,%2,%3,%4,%5,%6,%7,%8,%9,%10,%11,%12,%13,%14,%15,%16,%17,%18,%19,%20,%21,%22,%23,%24,%25,%26,%27,%28,%29,%30,%31,%32,%33,%34,%35,%36,%37,%38,%39,"
    "%40,%41,%42,%43,%44,%45,%46,%47,%48,%49,%50,%51,%52,%53,%54,%55,%56,%57,%58,%59,%60,%61,%62,%63,%64,%65,%66,%67,%68,%69,%70,%71,%72,%73,%74,%75,%76,"
    "%77,%78,%79,%80,%81,%82,%83,%84,%85,%86,%87,%88,%89,%90,%91,%92,%93,%94,%95,%96,%97,%98,%99,%100,%101,%102,%103,%104,%105,%106,%107,%108,%109,%110,"
    "%111,%112,%113,%114,%115,%116,%117,%118,%119,%120,%121,%122,%123,%124,%125,%126,%127"
    "}, da, db, p, 1, 1, 0, 1;\n}\n"
    :
      "+f"(d[0]),"+f"(d[1]),"+f"(d[2]),"+f"(d[3]),"+f"(d[4]),"+f"(d[5]),"+f"(d[6]),"+f"(d[7]),"+f"(d[8]),"+f"(d[9]),"+f"(d[10]),"+f"(d[11]),"+f"(d[12]),
      "+f"(d[13]),"+f"(d[14]),"+f"(d[15]),"+f"(d[16]),"+f"(d[17]),"+f"(d[18]),"+f"(d[19]),"+f"(d[20]),"+f"(d[21]),"+f"(d[22]),"+f"(d[23]),"+f"(d[24]),
      "+f"(d[25]),"+f"(d[26]),"+f"(d[27]),"+f"(d[28]),"+f"(d[29]),"+f"(d[30]),"+f"(d[31]),"+f"(d[32]),"+f"(d[33]),"+f"(d[34]),"+f"(d[35]),"+f"(d[36]),
      "+f"(d[37]),"+f"(d[38]),"+f"(d[39]),"+f"(d[40]),"+f"(d[41]),"+f"(d[42]),"+f"(d[43]),"+f"(d[44]),"+f"(d[45]),"+f"(d[46]),"+f"(d[47]),"+f"(d[48]),
      "+f"(d[49]),"+f"(d[50]),"+f"(d[51]),"+f"(d[52]),"+f"(d[53]),"+f"(d[54]),"+f"(d[55]),"+f"(d[56]),"+f"(d[57]),"+f"(d[58]),"+f"(d[59]),"+f"(d[60]),
      "+f"(d[61]),"+f"(d[62]),"+f"(d[63]),"+f"(d[64]),"+f"(d[65]),"+f"(d[66]),"+f"(d[67]),"+f"(d[68]),"+f"(d[69]),"+f"(d[70]),"+f"(d[71]),"+f"(d[72]),
      "+f"(d[73]),"+f"(d[74]),"+f"(d[75]),"+f"(d[76]),"+f"(d[77]),"+f"(d[78]),"+f"(d[79]),"+f"(d[80]),"+f"(d[81]),"+f"(d[82]),"+f"(d[83]),"+f"(d[84]),
      "+f"(d[85]),"+f"(d[86]),"+f"(d[87]),"+f"(d[88]),"+f"(d[89]),"+f"(d[90]),"+f"(d[91]),"+f"(d[92]),"+f"(d[93]),"+f"(d[94]),"+f"(d[95]),"+f"(d[96]),
      "+f"(d[97]),"+f"(d[98]),"+f"(d[99]),"+f"(d[100]),"+f"(d[101]),"+f"(d[102]),"+f"(d[103]),"+f"(d[104]),"+f"(d[105]),"+f"(d[106]),"+f"(d[107]),
      "+f"(d[108]),"+f"(d[109]),"+f"(d[110]),"+f"(d[111]),"+f"(d[112]),"+f"(d[113]),"+f"(d[114]),"+f"(d[115]),"+f"(d[116]),"+f"(d[117]),"+f"(d[118]),
      "+f"(d[119]),"+f"(d[120]),"+f"(d[121]),"+f"(d[122]),"+f"(d[123]),"+f"(d[124]),"+f"(d[125]),"+f"(d[126]),"+f"(d[127])
    : "r"(da), "r"(db), "r"(scale_d));
}
__device__ __forceinline__ void wgmma_ss_n168_t1(float (&d)[84], uint32_t da, uint32_t db, int scale_d) {
  asm volatile("{\n.reg .pred p;\n.reg .b32 hi;\n.reg .b64 da, db;\nsetp.ne.b32 p, %86, 0;\nmov.b32 hi, 0x40000040;\nmov.b64 da, {%84, hi};\nmov.b64 db, {%85, hi};\n"
    "wgmma.mma_async.sync.aligned.m64n168k16.f32.bf16.bf16 {"
    "%0,%1,%2,%3,%4,%5,%6,%7,%8,%9,%10,%11,%12,%13,%14,%15,%16,%17,%18,%19,%20,%21,%22,%23,%24,%25,%26,%27,%28,%29,%30,%31,%32,%33,%34,%35,%36,%37,%38,%39,"
    "%40,%41,%42,%43,%44,%45,%46,%47,%48,%49,%50,%51,%52,%53,%54,%55,%56,%57,%58,%59,%60,%61,%62,%63,%64,%65,%66,%67,%68,%69,%70,%71,%72,%73,%74,%75,%76,"
    "%77,%78,%79,%80,%81,%82,%83"
    "}, da, db, p, 1, 1, 0, 1;\n}\n"
    :
      "+f"(d[0]),"+f"(d[1]),"+f"(d[2]),"+f"(d[3]),"+f"(d[4]),"+f"(d[5]),"+f"(d[6]),"+f"(d[7]),"+f"(d[8]),"+f"(d[9]),"+f"(d[10]),"+f"(d[11]),"+f"(d[12]),
      "+f"(d[13]),"+f"(d[14]),"+f"(d[15]),"+f"(d[16]),"+f"(d[17]),"+f"(d[18]),"+f"(d[19]),"+f"(d[20]),"+f"(d[21]),"+f"(d[22]),"+f"(d[23]),"+f"(d[24]),
      "+f"(d[25]),"+f"(d[26]),"+f"(d[27]),"+f"(d[28]),"+f"(d[29]),"+f"(d[30]),"+f"(d[31]),"+f"(d[32]),"+f"(d[33]),"+f"(d[34]),"+f"(d[35]),"+f"(d[36]),
      "+f"(d[37]),"+f"(d[38]),"+f"(d[39]),"+f"(d[40]),"+f"(d[41]),"+f"(d[42]),"+f"(d[43]),"+f"(d[44]),"+f"(d[45]),"+f"(d[46]),"+f"(d[47]),"+f"(d[48]),
      "+f"(d[49]),"+f"(d[50]),"+f"(d[51]),"+f"(d[52]),"+f"(d[53]),"+f"(d[54]),"+f"(d[55]),"+f"(d[56]),"+f"(d[57]),"+f"(d[58]),"+f"(d[59]),"+f"(d[60]),
      "+f"(d[61]),"+f"(d[62]),"+f"(d[63]),"+f"(d[64]),"+f"(d[65]),"+f"(d[66]),"+f"(d[67]),"+f"(d[68]),"+f"(d[69]),"+f"(d[70]),"+f"(d[71]),"+f"(d[72]),
      "+f"(d[73]),"+f"(d[74]),"+f"(d[75]),"+f"(d[76]),"+f"(d[77]),"+f"(d[78]),"+f"(d[79]),"+f"(d[80]),"+f"(d[81]),"+f"(d[82]),"+f"(d[83])
    : "r"(da), "r"(db), "r"(scale_d));
}
__device__ __forceinline__ void wgmma_ss_n64_t0(float (&d)[32], uint32_t da, uint32_t db, int scale_d) {
  asm volatile("{\n.reg .pred p;\n.reg .b32 hi;\n.reg .b64 da, db;\nsetp.ne.b32 p, %34, 0;\nmov.b32 hi, 0x40000040;\nmov.b64 da, {%32, hi};\nmov.b64 db, {%33, hi};\n"
    "wgmma.mma_async.sync.aligned.m64n64k16.f32.bf16.bf16 {"
    "%0,%1,%2,%3,%4,%5,%6,%7,%8,%9,%10,%11,%12,%13,%14,%15,%16,%17,%18,%19,%20,%21,%22,%23,%24,%25,%26,%27,%28,%29,%30,%31"
    "}, da, db, p, 1, 1, 0, 0;\n}\n"
    :
      "+f"(d[0]),"+f"(d[1]),"+f"(d[2]),"+f"(d[3]),"+f"(d[4]),"+f"(d[5]),"+f"(d[6]),"+f"(d[7]),"+f"(d[8]),"+f"(d[9]),"+f"(d[10]),"+f"(d[11]),"+f"(d[12]),
      "+f"(d[13]),"+f"(d[14]),"+f"(d[15]),"+f"(d[16]),"+f"(d[17]),"+f"(d[18]),"+f"(d[19]),"+f"(d[20]),"+f"(d[21]),"+f"(d[22]),"+f"(d[23]),"+f"(d[24]),
      "+f"(d[25]),"+f"(d[26]),"+f"(d[27]),"+f"(d[28]),"+f"(d[29]),"+f"(d[30]),"+f"(d[31])
    : "r"(da), "r"(db), "r"(scale_d));
}
__device__ __forceinline__ void wgmma_ss_n64_t0_z(float (&d)[32], uint32_t da, uint32_t db) {
  asm volatile("{\n.reg .pred p;\n.reg .b32 hi;\n.reg .b64 da, db;\nsetp.ne.b32 p, 0, 0;\nmov.b32 hi, 0x40000040;\nmov.b64 da, {%32, hi};\nmov.b64 db, {%33, hi};\n"
    "wgmma.mma_async.sync.aligned.m64n64k16.f32.bf16.bf16 {"
    "%0,%1,%2,%3,%4,%5,%6,%7,%8,%9,%10,%11,%12,%13,%14,%15,%16,%17,%18,%19,%20,%21,%22,%23,%24,%25,%26,%27,%28,%29,%30,%31"
    "}, da, db, p, 1, 1, 0, 0;\n}\n"
    :
      "=f"(d[0]),"=f"(d[1]),"=f"(d[2]),"=f"(d[3]),"=f"(d[4]),"=f"(d[5]),"=f"(d[6]),"=f"(d[7]),"=f"(d[8]),"=f"(d[9]),"=f"(d[10]),"=f"(d[11]),"=f"(d[12]),
      "=f"(d[13]),"=f"(d[14]),"=f"(d[15]),"=f"(d[16]),"=f"(d[17]),"=f"(d[18]),"=f"(d[19]),"=f"(d[20]),"=f"(d[21]),"=f"(d[22]),"=f"(d[23]),"=f"(d[24]),
      "=f"(d[25]),"=f"(d[26]),"=f"(d[27]),"=f"(d[28]),"=f"(d[29]),"=f"(d[30]),"=f"(d[31])
    : "r"(da), "r"(db));
}
__device__ __forceinline__ void wgmma_rs_n256_t1(float (&d)[128], uint32_t a0, uint32_t a1, uint32_t a2, uint32_t a3, uint32_t db, int scale_d) {
  asm volatile("{\n.reg .pred p;\n.reg .b32 hi;\n.reg .b64 db;\nsetp.ne.b32 p, %133, 0;\nmov.b32 hi, 0x40000040;\nmov.b64 db, {%132, hi};\n"
    "wgmma.mma_async.sync.aligned.m64n256k16.f32.bf16.bf16 {"
    "%0,%1,%2,%3,%4,%5,%6,%7,%8,%9,%10,%11,%12,%13,%14,%15,%16,%17,%18,%19,%20,%21,%22,%23,%24,%25,%26,%27,%28,%29,%30,%31,%32,%33,%34,%35,%36,%37,%38,%39,"
    "%40,%41,%42,%43,%44,%45,%46,%47,%48,%49,%50,%51,%52,%53,%54,%55,%56,%57,%58,%59,%60,%61,%62,%63,%64,%65,%66,%67,%68,%69,%70,%71,%72,%73,%74,%75,%76,"
    "%77,%78,%79,%80,%81,%82,%83,%84,%85,%86,%87,%88,%89,%90,%91,%92,%93,%94,%95,%96,%97,%98,%99,%100,%101,%102,%103,%104,%105,%106,%107,%108,%109,%110,"
    "%111,%112,%113,%114,%115,%116,%117,%118,%119,%120,%121,%122,%123,%124,%125,%126,%127"
    "}, {%128,%129,%130,%131}, db, p, 1, 1, 1;\n}\n"
    :
      "+f"(d[0]),"+f"(d[1]),"+f"(d[2]),"+f"(d[3]),"+f"(d[4]),"+f"(d[5]),"+f"(d[6]),"+f"(d[7]),"+f"(d[8]),"+f"(d[9]),"+f"(d[10]),"+f"(d[11]),"+f"(d[12]),
      "+f"(d[13]),"+f"(d[14]),"+f"(d[15]),"+f"(d[16]),"+f"(d[17]),"+f"(d[18]),"+f"(d[19]),"+f"(d[20]),"+f"(d[21]),"+f"(d[22]),"+f"(d[23]),"+f"(d[24]),
      "+f"(d[25]),"+f"(d[26]),"+f"(d[27]),"+f"(d[28]),"+f"(d[29]),"+f"(d[30]),"+f"(d[31]),"+f"(d[32]),"+f"(d[33]),"+f"(d[34]),"+f"(d[35]),"+f"(d[36]),
      "+f"(d[37]),"+f"(d[38]),"+f"(d[39]),"+f"(d[40]),"+f"(d[41]),"+f"(d[42]),"+f"(d[43]),"+f"(d[44]),"+f"(d[45]),"+f"(d[46]),"+f"(d[47]),"+f"(d[48]),
      "+f"(d[49]),"+f"(d[50]),"+f"(d[51]),"+f"(d[52]),"+f"(d[53]),"+f"(d[54]),"+f"(d[55]),"+f"(d[56]),"+f"(d[57]),"+f"(d[58]),"+f"(d[59]),"+f"(d[60]),
      "+f"(d[61]),"+f"(d[62]),"+f"(d[63]),"+f"(d[64]),"+f"(d[65]),"+f"(d[66]),"+f"(d[67]),"+f"(d[68]),"+f"(d[69]),"+f"(d[70]),"+f"(d[71]),"+f"(d[72]),
      "+f"(d[73]),"+f"(d[74]),"+f"(d[75]),"+f"(d[76]),"+f"(d[77]),"+f"(d[78]),"+f"(d[79]),"+f"(d[80]),"+f"(d[81]),"+f"(d[82]),"+f"(d[83]),"+f"(d[84]),
      "+f"(d[85]),"+f"(d[86]),"+f"(d[87]),"+f"(d[88]),"+f"(d[89]),"+f"(d[90]),"+f"(d[91]),"+f"(d[92]),"+f"(d[93]),"+f"(d[94]),"+f"(d[95]),"+f"(d[96]),
      "+f"(d[97]),"+f"(d[98]),"+f"(d[99]),"+f"(d[100]),"+f"(d[101]),"+f"(d[102]),"+f"(d[103]),"+f"(d[104]),"+f"(d[105]),"+f"(d[106]),"+f"(d[107]),
      "+f"(d[108]),"+f"(d[109]),"+f"(d[110]),"+f"(d[111]),"+f"(d[112]),"+f"(d[113]),"+f"(d[114]),"+f"(d[115]),"+f"(d[116]),"+f"(d[117]),"+f"(d[118]),
      "+f"(d[119]),"+f"(d[120]),"+f"(d[121]),"+f"(d[122]),"+f"(d[123]),"+f"(d[124]),"+f"(d[125]),"+f"(d[126]),"+f"(d[127])
    : "r"(a0), "r"(a1), "r"(a2), "r"(a3), "r"(db), "r"(scale_d));
}
__device__ __forceinline__ void wgmma_rs_n128_t1(float (&d)[64], uint32_t a0, uint32_t a1, uint32_t a2, uint32_t a3, uint32_t db, int scale_d) {
  asm volatile("{\n.reg .pred p;\n.reg .b32 hi;\n.reg .b64 db;\nsetp.ne.b32 p, %69, 0;\nmov.b32 hi, 0x40000040;\nmov.b64 db, {%68, hi};\n"
    "wgmma.mma_async.sync.aligned.m64n128k16.f32.bf16.bf16 {"
    "%0,%1,%2,%3,%4,%5,%6,%7,%8,%9,%10,%11,%12,%13,%14,%15,%16,%17,%18,%19,%20,%21,%22,%23,%24,%25,%26,%27,%28,%29,%30,%31,%32,%33,%34,%35,%36,%37,%38,%39,"
    "%40,%41,%42,%43,%44,%45,%46,%47,%48,%49,%50,%51,%52,%53,%54,%55,%56,%57,%58,%59,%60,%61,%62,%63"
    "}, {%64,%65,%66,%67}, db, p, 1, 1, 1;\n}\n"
    :
      "+f"(d[0]),"+f"(d[1]),"+f"(d[2]),"+f"(d[3]),"+f"(d[4]),"+f"(d[5]),"+f"(d[6]),"+f"(d[7]),"+f"(d[8]),"+f"(d[9]),"+f"(d[10]),"+f"(d[11]),"+f"(d[12]),
      "+f"(d[13]),"+f"(d[14]),"+f"(d[15]),"+f"(d[16]),"+f"(d[17]),"+f"(d[18]),"+f"(d[19]),"+f"(d[20]),"+f"(d[21]),"+f"(d[22]),"+f"(d[23]),"+f"(d[24]),
      "+f"(d[25]),"+f"(d[26]),"+f"(d[27]),"+f"(d[28]),"+f"(d[29]),"+f"(d[30]),"+f"(d[31]),"+f"(d[32]),"+f"(d[33]),"+f"(d[34]),"+f"(d[35]),"+f"(d[36]),
      "+f"(d[37]),"+f"(d[38]),"+f"(d[39]),"+f"(d[40]),"+f"(d[41]),"+f"(d[42]),"+f"(d[43]),"+f"(d[44]),"+f"(d[45]),"+f"(d[46]),"+f"(d[47]),"+f"(d[48]),
      "+f"(d[49]),"+f"(d[50]),"+f"(d[51]),"+f"(d[52]),"+f"(d[53]),"+f"(d[54]),"+f"(d[55]),"+f"(d[56]),"+f"(d[57]),"+f"(d[58]),"+f"(d[59]),"+f"(d[60]),
      "+f"(d[61]),"+f"(d[62]),"+f"(d[63])
    : "r"(a0), "r"(a1), "r"(a2), "r"(a3), "r"(db), "r"(scale_d));
}
__device__ __forceinline__ void wgmma_rs_n128_t1_z(float (&d)[64], uint32_t a0, uint32_t a1, uint32_t a2, uint32_t a3, uint32_t db) {
  asm volatile("{\n.reg .pred p;\n.reg .b32 hi;\n.reg .b64 db;\nsetp.ne.b32 p, 0, 0;\nmov.b32 hi, 0x40000040;\nmov.b64 db, {%68, hi};\n"
    "wgmma.mma_async.sync.aligned.m64n128k16.f32.bf16.bf16 {"
    "%0,%1,%2,%3,%4,%5,%6,%7,%8,%9,%10,%11,%12,%13,%14,%15,%16,%17,%18,%19,%20,%21,%22,%23,%24,%25,%26,%27,%28,%29,%30,%31,%32,%33,%34,%35,%36,%37,%38,%39,"
    "%40,%41,%42,%43,%44,%45,%46,%47,%48,%49,%50,%51,%52,%53,%54,%55,%56,%57,%58,%59,%60,%61,%62,%63"
    "}, {%64,%65,%66,%67}, db, p, 1, 1, 1;\n}\n"
    :
      "=f"(d[0]),"=f"(d[1]),"=f"(d[2]),"=f"(d[3]),"=f"(d[4]),"=f"(d[5]),"=f"(d[6]),"=f"(d[7]),"=f"(d[8]),"=f"(d[9]),"=f"(d[10]),"=f"(d[11]),"=f"(d[12]),
      "=f"(d[13]),"=f"(d[14]),"=f"(d[15]),"=f"(d[16]),"=f"(d[17]),"=f"(d[18]),"=f"(d[19]),"=f"(d[20]),"=f"(d[21]),"=f"(d[22]),"=f"(d[23]),"=f"(d[24]),
      "=f"(d[25]),"=f"(d[26]),"=f"(d[27]),"=f"(d[28]),"=f"(d[29]),"=f"(d[30]),"=f"(d[31]),"=f"(d[32]),"=f"(d[33]),"=f"(d[34]),"=f"(d[35]),"=f"(d[36]),
      "=f"(d[37]),"=f"(d[38]),"=f"(d[39]),"=f"(d[40]),"=f"(d[41]),"=f"(d[42]),"=f"(d[43]),"=f"(d[44]),"=f"(d[45]),"=f"(d[46]),"=f"(d[47]),"=f"(d[48]),
      "=f"(d[49]),"=f"(d[50]),"=f"(d[51]),"=f"(d[52]),"=f"(d[53]),"=f"(d[54]),"=f"(d[55]),"=f"(d[56]),"=f"(d[57]),"=f"(d[58]),"=f"(d[59]),"=f"(d[60]),
      "=f"(d[61]),"=f"(d[62]),"=f"(d[63])
    : "r"(a0), "r"(a1), "r"(a2), "r"(a3), "r"(db));
}
__device__ __forceinline__ void wgmma_rs_n64_t1(float (&d)[32], uint32_t a0, uint32_t a1, uint32_t a2, uint32_t a3, uint32_t db, int scale_d) {
  asm volatile("{\n.reg .pred p;\n.reg .b32 hi;\n.reg .b64 db;\nsetp.ne.b32 p, %37, 0;\nmov.b32 hi, 0x40000040;\nmov.b64 db, {%36, hi};\n"
    "wgmma.mma_async.sync.aligned.m64n64k16.f32.bf16.bf16 {"
    "%0,%1,%2,%3,%4,%5,%6,%7,%8,%9,%10,%11,%12,%13,%14,%15,%16,%17,%18,%19,%20,%21,%22,%23,%24,%25,%26,%27,%28,%29,%30,%31"
    "}, {%32,%33,%34,%35}, db, p, 1, 1, 1;\n}\n"
    :
      "+f"(d[0]),"+f"(d[1]),"+f"(d[2]),"+f"(d[3]),"+f"(d[4]),"+f"(d[5]),"+f"(d[6]),"+f"(d[7]),"+f"(d[8]),"+f"(d[9]),"+f"(d[10]),"+f"(d[11]),"+f"(d[12]),
      "+f"(d[13]),"+f"(d[14]),"+f"(d[15]),"+f"(d[16]),"+f"(d[17]),"+f"(d[18]),"+f"(d[19]),"+f"(d[20]),"+f"(d[21]),"+f"(d[22]),"+f"(d[23]),"+f"(d[24]),
      "+f"(d[25]),"+f"(d[26]),"+f"(d[27]),"+f"(d[28]),"+f"(d[29]),"+f"(d[30]),"+f"(d[31])
    : "r"(a0), "r"(a1), "r"(a2), "r"(a3), "r"(db), "r"(scale_d));
}
__device__ __forceinline__ void wgmma_rs_n64_t1_z(float (&d)[32], uint32_t a0, uint32_t a1, uint32_t a2, uint32_t a3, uint32_t db) {
  asm volatile("{\n.reg .pred p;\n.reg .b32 hi;\n.reg .b64 db;\nsetp.ne.b32 p, 0, 0;\nmov.b32 hi, 0x40000040;\nmov.b64 db, {%36, hi};\n"
    "wgmma.mma_async.sync.aligned.m64n64k16.f32.bf16.bf16 {"
    "%0,%1,%2,%3,%4,%5,%6,%7,%8,%9,%10,%11,%12,%13,%14,%15,%16,%17,%18,%19,%20,%21,%22,%23,%24,%25,%26,%27,%28,%29,%30,%31"
    "}, {%32,%33,%34,%35}, db, p, 1, 1, 1;\n}\n"
    :
      "=f"(d[0]),"=f"(d[1]),"=f"(d[2]),"=f"(d[3]),"=f"(d[4]),"=f"(d[5]),"=f"(d[6]),"=f"(d[7]),"=f"(d[8]),"=f"(d[9]),"=f"(d[10]),"=f"(d[11]),"=f"(d[12]),
      "=f"(d[13]),"=f"(d[14]),"=f"(d[15]),"=f"(d[16]),"=f"(d[17]),"=f"(d[18]),"=f"(d[19]),"=f"(d[20]),"=f"(d[21]),"=f"(d[22]),"=f"(d[23]),"=f"(d[24]),
      "=f"(d[25]),"=f"(d[26]),"=f"(d[27]),"=f"(d[28]),"=f"(d[29]),"=f"(d[30]),"=f"(d[31])
    : "r"(a0), "r"(a1), "r"(a2), "r"(a3), "r"(db));
}
__device__ __forceinline__ void wgmma_rs_n64_t0_sw64(float (&d)[32], uint32_t a0, uint32_t a1, uint32_t a2, uint32_t a3, uint32_t db, int scale_d) {
  asm volatile("{\n.reg .pred p;\n.reg .b32 hi;\n.reg .b64 db;\nsetp.ne.b32 p, %37, 0;\nmov.b32 hi, 0x80000020;\nmov.b64 db, {%36, hi};\n"
    "wgmma.mma_async.sync.aligned.m64n64k16.f32.bf16.bf16 {"
    "%0,%1,%2,%3,%4,%5,%6,%7,%8,%9,%10,%11,%12,%13,%14,%15,%16,%17,%18,%19,%20,%21,%22,%23,%24,%25,%26,%27,%28,%29,%30,%31"
    "}, {%32,%33,%34,%35}, db, p, 1, 1, 0;\n}\n"
    :
      "+f"(d[0]),"+f"(d[1]),"+f"(d[2]),"+f"(d[3]),"+f"(d[4]),"+f"(d[5]),"+f"(d[6]),"+f"(d[7]),"+f"(d[8]),"+f"(d[9]),"+f"(d[10]),"+f"(d[11]),"+f"(d[12]),
      "+f"(d[13]),"+f"(d[14]),"+f"(d[15]),"+f"(d[16]),"+f"(d[17]),"+f"(d[18]),"+f"(d[19]),"+f"(d[20]),"+f"(d[21]),"+f"(d[22]),"+f"(d[23]),"+f"(d[24]),
      "+f"(d[25]),"+f"(d[26]),"+f"(d[27]),"+f"(d[28]),"+f"(d[29]),"+f"(d[30]),"+f"(d[31])
    : "r"(a0), "r"(a1), "r"(a2), "r"(a3), "r"(db), "r"(scale_d));
}
__device__ __forceinline__ void wgmma_rs_n64_t0_z_sw64(float (&d)[32], uint32_t a0, uint32_t a1, uint32_t a2, uint32_t a3, uint32_t db) {
  asm volatile("{\n.reg .pred p;\n.reg .b32 hi;\n.reg .b64 db;\nsetp.ne.b32 p, 0, 0;\nmov.b32 hi, 0x80000020;\nmov.b64 db, {%36, hi};\n"
    "wgmma.mma_async.sync.aligned.m64n64k16.f32.bf16.bf16 {"
    "%0,%1,%2,%3,%4,%5,%6,%7,%8,%9,%10,%11,%12,%13,%14,%15,%16,%17,%18,%19,%20,%21,%22,%23,%24,%25,%26,%27,%28,%29,%30,%31"
    "}, {%32,%33,%34,%35}, db, p, 1, 1, 0;\n}\n"
    :
      "=f"(d[0]),"=f"(d[1]),"=f"(d[2]),"=f"(d[3]),"=f"(d[4]),"=f"(d[5]),"=f"(d[6]),"=f"(d[7]),"=f"(d[8]),"=f"(d[9]),"=f"(d[10]),"=f"(d[11]),"=f"(d[12]),
      "=f"(d[13]),"=f"(d[14]),"=f"(d[15]),"=f"(d[16]),"=f"(d[17]),"=f"(d[18]),"=f"(d[19]),"=f"(d[20]),"=f"(d[21]),"=f"(d[22]),"=f"(d[23]),"=f"(d[24]),
      "=f"(d[25]),"=f"(d[26]),"=f"(d[27]),"=f"(d[28]),"=f"(d[29]),"=f"(d[30]),"=f"(d[31])
    : "r"(a0), "r"(a1), "r"(a2), "r"(a3), "r"(db));
}
__device__ __forceinline__ void wgmma_rs_n32_t1_sw64(float (&d)[16], uint32_t a0, uint32_t a1, uint32_t a2, uint32_t a3, uint32_t db, int scale_d) {
  asm volatile("{\n.reg .pred p;\n.reg .b32 hi;\n.reg .b64 db;\nsetp.ne.b32 p, %21, 0;\nmov.b32 hi, 0x80000020;\nmov.b64 db, {%20, hi};\n"
    "wgmma.mma_async.sync.aligned.m64n32k16.f32.bf16.bf16 {"
    "%0,%1,%2,%3,%4,%5,%6,%7,%8,%9,%10,%11,%12,%13,%14,%15"
    "}, {%16,%17,%18,%19}, db, p, 1, 1, 1;\n}\n"
    :
      "+f"(d[0]),"+f"(d[1]),"+f"(d[2]),"+f"(d[3]),"+f"(d[4]),"+f"(d[5]),"+f"(d[6]),"+f"(d[7]),"+f"(d[8]),"+f"(d[9]),"+f"(d[10]),"+f"(d[11]),"+f"(d[12]),
      "+f"(d[13]),"+f"(d[14]),"+f"(d[15])
    : "r"(a0), "r"(a1), "r"(a2), "r"(a3), "r"(db), "r"(scale_d));
}

struct Ring {
  int slot;
  uint32_t phase;
  template <int NS> __device__ __forceinline__ void next() {
    if (++slot == NS) { slot = 0; phase ^= 1; }
  }
};

struct Stager {
  uint32_t full, empty;
  uint32_t n0, n1;
  __device__ __forceinline__ void acquire(int b) {
    const uint32_t n = b ? n1 : n0;
    if (n > 0) mbar_wait(empty + 8 * b, (n - 1) & 1);
  }
  __device__ __forceinline__ void publish(int b, int lane, bool async_reader = true) {
    if (async_reader) fence_async_smem();
    __syncwarp();
    if (lane == 0) mbar_arrive(full + 8 * b);
    if (b) n1++; else n0++;
  }
};
struct DrainWarp {
  uint32_t full, empty;
  uint32_t n0, n1;
  __device__ __forceinline__ void wait(int b) {
    mbar_wait(full + 8 * b, (b ? n1 : n0) & 1);
    if (b) n1++; else n0++;
  }
  __device__ __forceinline__ void done(int b, int lane) {
    __syncwarp();
    if (lane == 0) mbar_arrive(empty + 8 * b);
  }
};
__device__ __forceinline__ uint4 lds128(uint32_t a) {
  uint4 v;
  asm volatile("ld.shared.v4.b32 {%0, %1, %2, %3}, [%4];" : "=r"(v.x), "=r"(v.y), "=r"(v.z), "=r"(v.w) : "r"(a) : "memory");
  return v;
}
template <int BYTES> __device__ __forceinline__ void warp_copy(uint8_t* dst, uint32_t src, int lane, int pause_ns) {
#pragma unroll 1
  for (int i = 0; i < BYTES; i += 2048) {
    if (pause_ns) __nanosleep(pause_ns);
    uint4 v[4];
#pragma unroll
    for (int j = 0; j < 4; j++) v[j] = lds128(src + i + j * 512 + lane * 16);
#pragma unroll
    for (int j = 0; j < 4; j++) {
      *reinterpret_cast<uint4*>(dst + i + j * 512 + lane * 16) = v[j];
    }
  }
}
struct StoreWarp {
  uint32_t full, empty;
  uint32_t n0, n1;
  int prev;
  __device__ __forceinline__ void wait(int b) {
    mbar_wait(full + 8 * b, (b ? n1 : n0) & 1);
    if (b) n1++; else n0++;
  }
  __device__ __forceinline__ void issued(int b, bool last) {
    bulk_commit();
    if (prev >= 0) {
      asm volatile("cp.async.bulk.wait_group.read 1;" ::: "memory");
      mbar_arrive(empty + 8 * prev);
    }
    prev = b;
    if (last) {
      bulk_wait_read();
      mbar_arrive(empty + 8 * b);
      prev = -1;
    }
  }
};

template <int HALF>
__device__ __forceinline__ void store_half_256(const float (&d)[128], uint32_t base, int warp4, int lane) {
  const int mi = lane >> 3;
  const int row = warp4 * 16 + (mi & 1) * 8 + (lane & 7);
  const uint32_t rbase = base + row * 128;
  const int rx = lane & 7;
#pragma unroll
  for (int j2 = 0; j2 < 16; j2 += 2) {
    const int jj = HALF * 16 + j2;
    const int cg = j2 + (mi >> 1);
    const uint32_t addr = rbase + (j2 >> 3) * 8192 + (((cg & 7) ^ rx) << 4);
    stmatrix_x4(addr, pack_bf16(d[4 * jj + 0], d[4 * jj + 1]), pack_bf16(d[4 * jj + 2], d[4 * jj + 3]),
                pack_bf16(d[4 * jj + 4], d[4 * jj + 5]), pack_bf16(d[4 * jj + 6], d[4 * jj + 7]));
  }
}

__device__ __forceinline__ void softmax_rowmax(const float (&s)[32], float& m0, float& m1) {
  float a0 = fmaxf(s[0], s[1]), a1 = fmaxf(s[2], s[3]);
#pragma unroll
  for (int j = 1; j < 8; j++) {
    a0 = fmaxf(a0, fmaxf(s[4 * j], s[4 * j + 1]));
    a1 = fmaxf(a1, fmaxf(s[4 * j + 2], s[4 * j + 3]));
  }
  a0 = fmaxf(a0, __shfl_xor_sync(0xffffffffu, a0, 1));
  a1 = fmaxf(a1, __shfl_xor_sync(0xffffffffu, a1, 1));
  a0 = fmaxf(a0, __shfl_xor_sync(0xffffffffu, a0, 2));
  a1 = fmaxf(a1, __shfl_xor_sync(0xffffffffu, a1, 2));
  m0 = fmaxf(m0, a0);
  m1 = fmaxf(m1, a1);
}

__device__ __forceinline__ void tma3d_mc_hint(uint32_t dst, const CUtensorMap* tm, int c0, int c1, int c2, uint32_t bar, uint64_t pol) {
  asm volatile("cp.async.bulk.tensor.3d.shared::cluster.global.mbarrier::complete_tx::bytes.multicast::cluster.L2::cache_hint [%0], [%1, {%3, %4, %5}], [%2], %6, %7;"
               ::"r"(dst), "l"(tm), "r"(bar), "r"(c0), "r"(c1), "r"(c2), "h"((uint16_t)3), "l"(pol) : "memory");
}
__device__ __forceinline__ void prefetch2d(const CUtensorMap* tm, int c0, int c1) {
  asm volatile("cp.async.bulk.prefetch.tensor.2d.L2.global.tile [%0, {%1, %2}];" ::"l"(tm), "r"(c0), "r"(c1) : "memory");
}
__device__ __forceinline__ void prefetch3d(const CUtensorMap* tm, int c0, int c1, int c2) {
  asm volatile("cp.async.bulk.prefetch.tensor.3d.L2.global.tile [%0, {%1, %2, %3}];" ::"l"(tm), "r"(c0), "r"(c1), "r"(c2) : "memory");
}
__device__ __forceinline__ void prefetch_bulk(const void* p, uint32_t bytes) {
  asm volatile("cp.async.bulk.prefetch.L2.global [%0], %1;" ::"l"(p), "r"(bytes) : "memory");
}

#define PACE_NS 300
constexpr float SC_A = 1.4426950408889634f * 0.18898223650461362f;

constexpr int G_STAGE = 49152;
constexpr int KV_OFF = 3 * G_STAGE;
constexpr int STG_OFF = KV_OFF + 16384;
constexpr int BAR_OFF = STG_OFF + 65536;
constexpr int MEGA_SMEM = BAR_OFF + 512;
constexpr int A_NS = 5;

enum : int { F_P0 = 0, F_ZERO = 1, F_DONE = 2, F_KV = 8, F_OA = 24, F_COUNT = 32 };
__device__ unsigned g_flag[F_COUNT];

__device__ __forceinline__ void flag_add(int f) {
  asm volatile("red.relaxed.gpu.global.add.u32 [%0], 1;" ::"l"(&g_flag[f]) : "memory");
}
__device__ __forceinline__ void fence_gpu() { asm volatile("fence.acq_rel.gpu;" ::: "memory"); }
__device__ __forceinline__ void fence_async_global() { asm volatile("fence.proxy.async.global;" ::: "memory"); }
__device__ __forceinline__ void flag_wait(int f, unsigned target) {
  for (int n = 0;; n++) {
    unsigned v;
    asm volatile("ld.acquire.gpu.global.u32 %0, [%1];" : "=r"(v) : "l"(&g_flag[f]) : "memory");
    if (v >= target) break;
    if (n > (1 << 22)) __trap();
    __nanosleep(64);
  }
}

__device__ __forceinline__ int ctaid_v() { int x; asm volatile("mov.u32 %0, %%ctaid.x;" : "=r"(x)); return x; }
__device__ __forceinline__ int tid_v() { int x; asm volatile("mov.u32 %0, %%tid.x;" : "=r"(x)); return x; }
__device__ __forceinline__ uint32_t rank_v() { uint32_t x; asm volatile("mov.u32 %0, %%cluster_ctarank;" : "=r"(x)); return x; }
#define COORDS_P01() const int cl = ctaid_v() >> 1, mp = cl & 7, g8 = cl >> 3; const uint32_t rank = rank_v();
#define COORDS_P2() const int cl = ctaid_v() >> 1, h = cl & 15, grp = cl >> 4; const uint32_t rank = rank_v(); \
  const bool is_main = cl < 64; const int nitems = is_main ? 2 : 8; \
  const int bA = rank == 0 ? 0 : 1, bB = rank == 0 ? 3 : 2;

#define SKEW 5
struct Params {
  CUtensorMap ax, wqkv, ckv, wk, wv, x, wq, wo, oa, awo, out;
};

__global__ void __cluster_dims__(2, 1, 1) __launch_bounds__(384, 1)
mega_kernel(const __grid_constant__ Params P, __nv_bfloat16* __restrict__ out) {
  extern __shared__ __align__(1024) uint8_t smem[];
  const uint32_t sb = smem_u32(smem);
  const uint32_t gfull = sb + BAR_OFF, gempty = gfull + 24, kfull = gempty + 24, kempty = kfull + 16;
  const uint32_t sfull = kempty + 16, sempty = sfull + 32, afull = sempty + 32, aempty = afull + 40;
  const uint32_t oafull = aempty + 40;
  const uint32_t p0done = oafull + 16, p0all = p0done + 8, p0stg = p0all + 8;
  const uint32_t kvdone = p0stg + 16;
  const uint32_t kviss = p0stg + 24;
  const int tid = threadIdx.x, wg = __shfl_sync(0xffffffffu, tid >> 7, 0), lane = tid & 31;
  if (tid == 256) {
#pragma unroll
    for (int i = 0; i < 32; i++)
      mbar_init(gfull + 8 * i, i < 3 ? 1 : i < 6 ? 4 : i < 8 ? 1 : i < 10 ? 2 : i < 14 ? 4 : i < 23 ? 1 : i < 30 ? 4 : i == 30 ? 2 : 1);
    mbar_init(p0stg, 4);
    mbar_init(p0stg + 8, 4);
    mbar_init(kvdone, 1);
    mbar_init(kviss, 1);
    asm volatile("fence.mbarrier_init.release.cluster;" ::: "memory");
    if (blockIdx.x < 128) {
      const int row0 = ((blockIdx.x >> 1) & 7) * 256 + (blockIdx.x & 1) * 128;
      for (int kb = 0; kb < 3; kb++) {
        mbar_expect_tx(gfull + 8 * kb, 40960);
        tma2d(sb + kb * G_STAGE, &P.ax, kb * 64, row0, gfull + 8 * kb);
      }
    }
  }
  __syncthreads();
  cluster_sync();

  if (wg == 2) {
    reg_dec<40>();
    const int warp = tid >> 5;
    if (tid == 256) {
      if (blockIdx.x < 128) {
        COORDS_P01()
        Ring r{0, 0};
        const int row0 = mp * 256 + rank * 128;
        for (int kb = 0; kb < 7; kb++) {
          const uint32_t st = sb + r.slot * G_STAGE, fb = gfull + 8 * r.slot;
          if (kb >= 3) {
            mbar_wait(gempty + 8 * r.slot, r.phase ^ 1);
            mbar_expect_tx(fb, 40960);
            tma2d(st, &P.ax, kb * 64, row0, fb);
          }
#pragma unroll
          for (int i = 0; i < 3; i++)
            tma2d_mc(st + 16384 + i * 8192 + rank * 4096, &P.wqkv, g8 * 168 + i * 64, kb * 64 + rank * 32, fb);
          r.next<3>();
        }
        uint64_t pol_stream;
        asm volatile("createpolicy.fractional.L2::evict_first.b64 %0, 1.0;" : "=l"(pol_stream));
        for (int i = 0; i < 64; i++) {
          const int sub = i >> 4, kb = i & 15;
          const int nt = sub * 8 + g8;
          const CUtensorMap* tw = (nt & 1) ? &P.wv : &P.wk;
          const uint32_t st = sb + r.slot * G_STAGE, fb = gfull + 8 * r.slot;
          mbar_wait(gempty + 8 * r.slot, r.phase ^ 1);
          mbar_expect_tx(fb, 49152);
          tma2d(st, &P.ckv, kb * 64, row0, fb);
          tma3d_mc_hint(st + 16384 + rank * 16384, tw, 0, kb * 64, (nt >> 1) * 4 + rank * 2, fb, pol_stream);
          r.next<3>();
          if (kb == 2 && sub < 3) {
            const int nn = nt + 8, u = mp * 2 + rank;
            const CUtensorMap* tn = (nn & 1) ? &P.wv : &P.wk;
            prefetch3d(tn, 0, u * 64, (nn >> 1) * 4);
            prefetch3d(tn, 0, u * 64, (nn >> 1) * 4 + 2);
          }
          if (i >= 52 && i < 59) {
            const int h = cl & 15, grp = cl >> 4, bA = rank == 0 ? 0 : 1, bB = rank == 0 ? 3 : 2, q = i - 52;
            if ((q & 3) == grp) prefetch3d(&P.wq, 0, q * 64, h * 4 + rank * 2);
            prefetch2d(&P.x, q * 64, 256 * (7 - grp) + 64 * bA);
            prefetch2d(&P.x, q * 64, 256 * (7 - grp) + 64 * bB);
          }
        }
        for (int s = 0; s < 3; s++) { mbar_wait(gempty + 8 * r.slot, r.phase ^ 1); r.next<3>(); }
        mbar_wait(kviss, 0);
      }
      COORDS_P2()
      Ring r{0, 0};
      bool first_lap = is_main;
      auto acquire = [&](uint32_t bytes) -> uint32_t {
        if (first_lap && r.slot == 4) { mbar_wait(kvdone, 0); first_lap = false; }
        mbar_wait(aempty + 8 * r.slot, r.phase ^ 1);
        mbar_expect_tx(afull + 8 * r.slot, bytes);
        return sb + r.slot * 32768;
      };
      const CUtensorMap* tx = is_main ? &P.x : &P.oa;
      const CUtensorMap* tw = is_main ? &P.wq : &P.awo;
      const int nb0 = (is_main ? h * 4 : (cl - 64) * 4) + rank * 2;
      for (int item = 0; item < nitems; item++) {
        const int j = is_main ? (item == 0 ? 7 - grp : grp) : item;
        const int rowA = 256 * j + 64 * bA, rowB = 256 * j + 64 * bB;
        if (!is_main) { flag_wait(F_OA + j, 32); fence_async_global(); }
        for (int kb = 0; kb < 7; kb++) {
          {
            const uint32_t st = acquire(32768), fb = afull + 8 * r.slot;
            tma3d_mc(st + rank * 16384, tw, 0, kb * 64, nb0, fb);
            r.next<A_NS>();
          }
          if ((kb & 1) == 0) {
            const uint32_t st = acquire(kb < 6 ? 32768 : 16384), fb = afull + 8 * r.slot;
            tma2d(st, tx, kb * 64, rowA, fb);
            tma2d(st + 8192, tx, kb * 64, rowB, fb);
            if (kb < 6) {
              tma2d(st + 16384, tx, kb * 64 + 64, rowA, fb);
              tma2d(st + 24576, tx, kb * 64 + 64, rowB, fb);
            }
            r.next<A_NS>();
          }
        }
        if (!is_main) continue;
        if (item == 0) { flag_wait(F_KV + h, 64); fence_async_global(); }
        const int n = 4 * j + 4;
        const uint8_t* gk = g_K + (size_t)h * 32 * 32768 + rank * 16384;
        const uint8_t* gv = g_V + (size_t)h * 32 * 32768 + rank * 16384;
        for (int u = 0; u < 2 * n; u++) {
          const uint8_t* src;
          if (u == 0) src = gk + (size_t)(n - 1) * 32768;
          else if (u == 2 * n - 1) src = gv;
          else {
            const int t = n - 1 - ((u - 1) >> 1);
            src = (u & 1) ? gk + (size_t)(t - 1) * 32768 : gv + (size_t)t * 32768;
          }
          const uint32_t st = acquire(32768);
          bulk_load_mc(st + rank * 16384, src, 16384, afull + 8 * r.slot);
          r.next<A_NS>();
          if (item == 0 && grp == 3 && u >= 8 && u < 15) prefetch2d(&P.wo, (u - 8) * 64, h * 256 + rank * 128);
        }
        for (int u = -1; u < 6; u++) {
          const uint32_t st = acquire(32768);
          if (u >= 0) tma2d_mc(st + rank * 16384, &P.wo, ((1 + (u >> 1) * 2 + rank + h) % 7) * 64, h * 256 + (u & 1) * 128, afull + 8 * r.slot);
          else tma2d_mc(st + rank * 16384, &P.wo, (h % 7) * 64, h * 256 + rank * 128, afull + 8 * r.slot);
          r.next<A_NS>();
        }
      }
    } else if (warp == 9 || warp == 10) {
      const int w = warp - 9;
      const uint32_t stg = sb + STG_OFF + w * 32768;
      auto clear_acc = [&]() {
        const int nthr = gridDim.x * 64, me = blockIdx.x * 64 + (tid - 288);
        for (int i = me; i < SEQ * 56; i += nthr) {
          const int row = i / 56, c = i - row * 56;
          *reinterpret_cast<uint4*>(out + (size_t)row * OUTW + DM + c * 8) = make_uint4(0, 0, 0, 0);
        }
      };
      if (blockIdx.x >= 128) {
        clear_acc();
        fence_async_global();
        fence_gpu();
        __syncwarp();
        if (lane == 0) flag_add(F_ZERO);
      }
      uint32_t n0 = 0, n1 = 0;
      if (blockIdx.x < 128) {
        COORDS_P01()
        if (lane == 0) {
          const int rb = mp * 4 + rank * 2 + w;
          mbar_wait(p0stg + 8 * w, 0);
          for (int hh = 0; hh < 6; hh++) {
            const int gh = g8 * 6 + hh, which = gh >> 4, hd = gh & 15;
            uint8_t* dst = which == 0 ? g_QA + (size_t)(hd * 32 + rb) * 4096
                                      : (which == 1 ? g_KVA + (size_t)(hd * 33 + rb) * 8192 : g_KVA + (size_t)(hd * 33 + rb + 1) * 8192 + 4096);
            bulk_store(dst, stg + hh * 4096, 4096);
          }
          bulk_commit();
          bulk_wait_all();
          mbar_arrive(p0done);
        }
        __syncwarp();
        DrainWarp dw{sfull + 16 * w, sempty + 16 * w, 0, 0};
        for (int sub = 0; sub < 4; sub++) {
          const int nt = sub * 8 + g8, t = mp * 4 + rank * 2 + w;
          uint8_t* dst = ((nt & 1) ? g_V : g_K) + (size_t)((nt >> 1) * 32 + t) * 32768;
          for (int b = 0; b < 2; b++) {
            dw.wait(b);
            warp_copy<16384>(dst + b * 16384, stg + b * 16384, lane, sub < 3 ? PACE_NS : 0);
            dw.done(b, lane);
          }
          if (sub == 0) clear_acc();
          if (sub == 2) {
            fence_async_global();
            fence_gpu();
            __syncwarp();
            if (lane < 3) flag_add(F_KV + ((lane * 8 + g8) >> 1));
            if (lane == 5) flag_add(F_ZERO);
          }
        }
        fence_async_global();
        fence_gpu();
        __syncwarp();
        if (lane == 0) flag_add(F_KV + ((24 + g8) >> 1));
        mbar_wait(oafull + 8 * w, 1);
        fence_async_global();
        fence_gpu();
        __syncwarp();
        if (lane == 0) flag_add(F_OA + mp);
        n0 = dw.n0; n1 = dw.n1;
      }
      if (lane == 0) {
        COORDS_P2()
        StoreWarp sw{sfull + 16 * w, sempty + 16 * w, n0, n1, -1};
        for (int item = 0; item < nitems; item++) {
          const int j = is_main ? (item == 0 ? 7 - grp : grp) : item;
          const int rb = 4 * j + (w == 0 ? bA : bB);
          if (is_main) {
            if (item == 0) { flag_wait(F_ZERO, 264); fence_async_global(); }
            for (int u = 0; u < 4; u++) {
              const int b = u & 1;
              sw.wait(b);
              for (int e = 0; e < (u > 0 ? 2 : 1); e++)
                asm volatile("cp.reduce.async.bulk.tensor.2d.global.shared::cta.add.tile.bulk_group [%0, {%2, %3}], [%1];"
                             ::"l"(&P.out), "r"(stg + b * 16384 + e * 8192), "r"(DM + (((u > 0 ? 2 * u - 1 + e : 0) + h) % 7) * 64), "r"(rb * 64) : "memory");
              sw.issued(b, u == 3);
            }
          } else {
            for (int b = 0; b < 2; b++) {
              sw.wait(b);
              for (int e = 0; e < 2; e++) {
                const int blk = (cl - 64) * 4 + b * 2 + e;
                if (blk < 7)
                  asm volatile("cp.async.bulk.tensor.2d.global.shared::cta.tile.bulk_group [%0, {%2, %3}], [%1];"
                               ::"l"(&P.out), "r"(stg + b * 16384 + e * 8192), "r"(blk * 64), "r"(rb * 64) : "memory");
              }
              sw.issued(b, b == 1);
            }
          }
        }
        bulk_wait_all();
      }
    } else if (tid == 352 && blockIdx.x < 128) {
      COORDS_P01()
      Ring rk{0, 0};
      mbar_wait(p0done, 0);
      fence_gpu();
      flag_add(F_P0);
      flag_wait(F_P0, 128);
      fence_async_global();
      mbar_arrive(p0all);
      for (int item = 0; item < 2; item++) {
        const uint8_t* src = g_KVA + (size_t)(item * 8 + g8) * 33 * 8192;
        for (int t = 0; t < 33; t++) {
          if (item == 0 && t == 20) {
            const int u = mp * 2 + rank;
            const uint8_t* kv2 = g_KVA + (size_t)(8 + g8) * 33 * 8192;
            if (u == 0) { prefetch_bulk(kv2, 4096); prefetch_bulk(kv2 + 8192, 8192); }
            else prefetch_bulk(kv2 + u * 16384, 16384);
            if (u == 15) prefetch_bulk(kv2 + 32 * 8192 + 4096, 4096);
            prefetch_bulk(g_QA + (size_t)((8 + g8) * 32 + mp * 4 + rank * 2) * 4096, 8192);
          }
          const uint32_t fb = kfull + 8 * rk.slot;
          mbar_wait(kempty + 8 * rk.slot, rk.phase ^ 1);
          const uint32_t lo = t == 32 ? 4096 : 0, bytes = (t == 0 || t == 32) ? 4096 : 8192;
          mbar_expect_tx(fb, bytes);
          bulk_load(sb + KV_OFF + rk.slot * 8192 + lo, src + t * 8192 + lo, bytes, fb);
          rk.next<2>();
        }
      }
      mbar_arrive(kviss);
      for (int i = 0; i < 2; i++) { mbar_wait(kempty + 8 * rk.slot, rk.phase ^ 1); rk.next<2>(); }
      mbar_arrive(kvdone);
    }
    __syncwarp();
  } else {
    reg_inc<232>();
    const int warp4 = __shfl_sync(0xffffffffu, (tid >> 5) & 3, 0);
    if (wg == 1) bar_arrive(3, 256);
    if (blockIdx.x < 128) {
      {
        COORDS_P01()
        const int wtid = tid_v() & 127, lane = wtid & 31;
        const uint32_t stg = sb + STG_OFF + wg * 32768;
        Ring r{0, 0};
        float d[84];
        int prev = 0;
        for (int kb = 0; kb < 7; kb++) {
          const uint32_t st = sb + r.slot * G_STAGE;
          mbar_wait(gfull + 8 * r.slot, r.phase);
          const uint32_t da = desc_kmajor(st + wg * 8192), db = desc_nmajor128(st + 16384);
          wgmma_fence();
#pragma unroll
          for (int kk = 0; kk < 4; kk++) wgmma_ss_n168_t1(d, da + kk * 2, db + kk * 128, (kb | kk) != 0);
          wgmma_commit();
          if (kb > 0) {
            wgmma_wait<1>();
            if (wtid < 2) mbar_arrive_cta(gempty + 8 * prev, wtid);
          }
          prev = r.slot;
          r.next<3>();
        }
        wgmma_wait<0>();
        fence_regs(d);
        if (wtid < 2) mbar_arrive_cta(gempty + 8 * prev, wtid);
        const int q = lane & 3;
        const int r0 = warp4 * 16 + (lane >> 2);
        const int x0 = (r0 >> 1) & 3;
        const uint32_t a0 = stg + r0 * 64;
        const int hi = q >> 1;
        uint32_t oa[4], ob[4];
#pragma unroll
        for (int c = 0; c < 4; c++) {
          oa[c] = a0 + ((c ^ x0) << 4) + q * 4;
          ob[c] = a0 + ((((c + hi) & 3) ^ x0) << 4) + ((q * 4 + 8) & 15);
        }
#pragma unroll
        for (int jj = 0; jj < 21; jj++) {
          const int hh = (jj * 8) / 28, d0 = (jj * 8) % 28;
          uint32_t addr;
          if (d0 == 24) addr = hi ? oa[0] - 8 + (hh + 1) * 4096 : oa[3] + hh * 4096;
          else if ((d0 & 7) == 0) addr = oa[d0 >> 3] + hh * 4096;
          else addr = ob[d0 >> 3] + hh * 4096;
          asm volatile("st.shared.b32 [%0], %1;" ::"r"(addr), "r"(pack_bf16(d[4 * jj], d[4 * jj + 1])) : "memory");
          asm volatile("st.shared.b32 [%0], %1;" ::"r"(addr + 512), "r"(pack_bf16(d[4 * jj + 2], d[4 * jj + 3])) : "memory");
        }
#pragma unroll
        for (int i = 0; i < 3; i++) {
          const int idx = i * 128 + wtid, hh = idx >> 6, rr = idx & 63;
          const uint32_t padv = (g8 * 6 + hh) >= 32 ? 0x00003F80u : 0u;
          const uint32_t a = stg + hh * 4096 + rr * 64 + ((3 ^ ((rr >> 1) & 3)) << 4) + 8;
          asm volatile("st.shared.v2.b32 [%0], {%1, %2};" ::"r"(a), "r"(padv), "r"(0u) : "memory");
        }
        fence_async_smem();
        __syncwarp();
        if (lane == 0) mbar_arrive(p0stg + 8 * wg);
      }
      {
        float d[128], s[32], o[16];
        uint32_t p[16], qa[8];
        const int lane = tid_v() & 31;
        Ring r{1, 0};
        Stager sg{sfull + 16 * wg, sempty + 16 * wg, 0, 0};
        auto load_q = [&](int item) {
          COORDS_P01()
          const int hA = item * 8 + g8, rb = mp * 4 + rank * 2 + wg;
          const int ln = tid_v() & 31;
          const int q = ln & 3, r0 = warp4 * 16 + (ln >> 2), r1 = r0 + 8;
          const uint8_t* qp = g_QA + (size_t)(hA * 32 + rb) * 4096;
          const int x0 = (r0 >> 1) & 3, x1 = (r1 >> 1) & 3;
#pragma unroll
          for (int ks = 0; ks < 2; ks++) {
            qa[4 * ks + 0] = __ldcg(reinterpret_cast<const uint32_t*>(qp + r0 * 64 + (((2 * ks) ^ x0) << 4) + q * 4));
            qa[4 * ks + 1] = __ldcg(reinterpret_cast<const uint32_t*>(qp + r1 * 64 + (((2 * ks) ^ x1) << 4) + q * 4));
            qa[4 * ks + 2] = __ldcg(reinterpret_cast<const uint32_t*>(qp + r0 * 64 + (((2 * ks + 1) ^ x0) << 4) + q * 4));
            qa[4 * ks + 3] = __ldcg(reinterpret_cast<const uint32_t*>(qp + r1 * 64 + (((2 * ks + 1) ^ x1) << 4) + q * 4));
          }
        };
        Ring rk{0, 0};
        float n0, n1;
        auto gemm_issue = [&](int kb) {
          const uint32_t st = sb + r.slot * G_STAGE;
          mbar_wait(gfull + 8 * r.slot, r.phase);
          const uint32_t da = desc_kmajor(st + wg * 8192), db = desc_nmajor128(st + 16384);
          wgmma_fence();
#pragma unroll
          for (int kk = 0; kk < 4; kk++) wgmma_ss_n256_t1(d, da + kk * 2, db + kk * 128, (kb | kk) != 0);
          wgmma_commit();
        };
        auto gemm_done = [&](int kb) {
          wgmma_wait<0>();
          fence_regs(d);
          if (lane < 2 && warp4 == 1) mbar_arrive_cta(gempty + 8 * r.slot, lane);
          r.next<3>();
          if (kb == 15) {
            const uint32_t stg = sb + STG_OFF + wg * 32768;
            sg.acquire(0);
            store_half_256<0>(d, stg, warp4, tid_v() & 31);
            sg.publish(0, lane, false);
            sg.acquire(1);
            store_half_256<1>(d, stg + 16384, warp4, tid_v() & 31);
            sg.publish(1, lane, false);
          }
        };
        auto attn_issue = [&](int t) -> int {
          const uint32_t kv = sb + KV_OFF + rk.slot * 8192;
          const int ks = rk.slot;
          if (t == 0) {
            n0 = INFINITY; n1 = INFINITY;
#pragma unroll
            for (int j = 0; j < 16; j++) p[j] = 0;
          }
          mbar_wait(kfull + 8 * ks, rk.phase);
          rk.next<2>();
          fence_regs(qa);
          fence_regs(p);
          fence_regs(o);
          bar_sync(3 + wg, 256);
          wgmma_fence();
          const uint32_t dv = desc_kmajor(t > 0 ? kv + 4096 : kv);
#pragma unroll
          for (int kk = 0; kk < 4; kk++)
            wgmma_rs_n32_t1_sw64(o, p[4 * kk], p[4 * kk + 1], p[4 * kk + 2], p[4 * kk + 3], dv + kk * 64, t | kk);
          const uint32_t dk = desc_kmajor(kv);
          wgmma_rs_n64_t0_z_sw64(s, qa[0], qa[1], qa[2], qa[3], dk);
          wgmma_rs_n64_t0_sw64(s, qa[4], qa[5], qa[6], qa[7], dk + 2, 1);
          wgmma_commit();
          return ks;
        };
        auto attn_softmax = [&](int t, int ks) {
          if (lane == 0 && warp4 == 0) mbar_arrive(kempty + 8 * ks);
          fence_regs(s);
          fence_regs(o);
          fence_regs(p);
          fence_regs(qa);
          bool redo = true;
          if (t > 0) {
#pragma unroll
            for (int jj = 0; jj < 8; jj++) {
              p[2 * jj] = pack_bf16(ex2(fmaf(s[4 * jj], SC_A, n0)), ex2(fmaf(s[4 * jj + 1], SC_A, n0)));
              p[2 * jj + 1] = pack_bf16(ex2(fmaf(s[4 * jj + 2], SC_A, n1)), ex2(fmaf(s[4 * jj + 3], SC_A, n1)));
            }
            uint32_t mx = __vimax3_u16x2(p[0], p[1], p[2]);
#pragma unroll
            for (int j = 3; j < 15; j += 2) mx = __vimax3_u16x2(mx, p[j], p[j + 1]);
            mx = __vimax3_u16x2(mx, p[15], p[15]);
            redo = __any_sync(0xffffffffu, max(mx & 0xffffu, mx >> 16) > 0x5380u);
          }
          if (redo) {
            float x0 = -INFINITY, x1 = -INFINITY;
            softmax_rowmax(s, x0, x1);
            const float w0 = fminf(n0, -x0 * SC_A), w1 = fminf(n1, -x1 * SC_A);
            const float a0 = ex2(w0 - n0), a1 = ex2(w1 - n1);
            n0 = w0; n1 = w1;
#pragma unroll
            for (int j = 0; j < 4; j++) { o[4 * j] *= a0; o[4 * j + 1] *= a0; o[4 * j + 2] *= a1; o[4 * j + 3] *= a1; }
#pragma unroll
            for (int jj = 0; jj < 8; jj++) {
              p[2 * jj] = pack_bf16(ex2(fmaf(s[4 * jj], SC_A, n0)), ex2(fmaf(s[4 * jj + 1], SC_A, n0)));
              p[2 * jj + 1] = pack_bf16(ex2(fmaf(s[4 * jj + 2], SC_A, n1)), ex2(fmaf(s[4 * jj + 3], SC_A, n1)));
            }
          }
          fence_regs(p);
          fence_regs(o);
        };
        auto item_end = [&](int item) {
          const int ks = rk.slot;
          mbar_wait(kfull + 8 * ks, rk.phase);
          rk.next<2>();
          const uint32_t dv = desc_kmajor(sb + KV_OFF + ks * 8192 + 4096);
          wgmma_fence();
#pragma unroll
          for (int kk = 0; kk < 4; kk++) wgmma_rs_n32_t1_sw64(o, p[4 * kk], p[4 * kk + 1], p[4 * kk + 2], p[4 * kk + 3], dv + kk * 64, 1);
          wgmma_commit();
          if (item == 0) load_q(1);
          wgmma_wait<0>();
          fence_regs(o);
          fence_regs(p);
          if (lane == 0 && warp4 == 0) mbar_arrive(kempty + 8 * ks);
          COORDS_P01()
          const int hA = item * 8 + g8, rb = mp * 4 + rank * 2 + wg;
          const int ln = tid_v() & 31, q = ln & 3;
          const float l0 = __shfl_sync(0xffffffffu, o[12], (ln & ~3) | 2), l1 = __shfl_sync(0xffffffffu, o[14], (ln & ~3) | 2);
          const float i0 = rcp(l0), i1 = rcp(l1);
          __nv_bfloat16* op = g_oA + (size_t)(rb * 64 + warp4 * 16 + (ln >> 2)) * DM + hA * 28 + q * 2;
#pragma unroll
          for (int jj = 0; jj < 4; jj++) {
            if (jj < 3 || q < 2) {
              *reinterpret_cast<uint32_t*>(op + jj * 8) = pack_bf16(o[4 * jj] * i0, o[4 * jj + 1] * i0);
              *reinterpret_cast<uint32_t*>(op + 8 * DM + jj * 8) = pack_bf16(o[4 * jj + 2] * i1, o[4 * jj + 3] * i1);
            }
          }
          __syncwarp();
          if (ln == 0) mbar_arrive(oafull + 8 * wg);
        };
#pragma unroll 1
        for (int i = 0; i < SKEW; i++) {
          bar_sync(3 + wg, 256);
          gemm_issue(i);
          bar_arrive(3 + (wg ^ 1), 256);
          gemm_done(i);
        }
        mbar_wait(p0all, 0);
        load_q(0);
#pragma unroll 1
        for (int item = 0; item < 2; item++) {
          const int nf = item == 0 ? 32 : 32 - SKEW;
#pragma unroll 1
          for (int t = 0; t < nf; t++) {
            const int kb = (t + SKEW) & 15;
            const int ks = attn_issue(t);
            gemm_issue(kb);
            bar_arrive(3 + (wg ^ 1), 256);
            wgmma_wait<1>();
            attn_softmax(t, ks);
            gemm_done(kb);
          }
#pragma unroll 1
          for (int t = nf; t < 32; t++) {
            const int ks = attn_issue(t);
            bar_arrive(3 + (wg ^ 1), 256);
            wgmma_wait<0>();
            attn_softmax(t, ks);
          }
          item_end(item);
        }
      }
    }
    {
      COORDS_P2()
      const int wtid = tid_v() & 127, lane = wtid & 31;
      const int b = wg == 0 ? bA : bB;
      const uint32_t qs = sb + STG_OFF + wg * 32768;
      Stager sg{sfull + 16 * wg, sempty + 16 * wg, is_main ? 4u : 0u, is_main ? 4u : 0u};
      constexpr float SC = 0.0625f * 1.4426950408889634f;
      Ring r{0, 0};
      float o[128];
      float s[32];
      uint32_t pA[16], pB[16];
      auto release = [&](int slot) { if (wtid < 2) mbar_arrive_cta(aempty + 8 * slot, wtid); };
      auto skip = [&]() { mbar_wait(afull + 8 * r.slot, r.phase); release(r.slot); r.next<A_NS>(); };
      auto take = [&]() -> int { mbar_wait(afull + 8 * r.slot, r.phase); const int sl = r.slot; r.next<A_NS>(); return sl; };

      auto project = [&](bool publish) {
#pragma unroll
        for (int i = 0; i < 128; i++) o[i] = 0.f;
        fence_regs(o);
        int xslot = 0, prevw = 0, prevx = -1;
        for (int kb = 0; kb < 7; kb++) {
          int relx = -1;
          const int ws = take();
          if ((kb & 1) == 0) {
            relx = prevx;
            xslot = take();
          }
          const uint32_t da = desc_kmajor(sb + xslot * 32768 + (kb & 1) * 16384 + wg * 8192);
          const uint32_t db = desc_nmajor128(sb + ws * 32768);
          wgmma_fence();
#pragma unroll
          for (int kk = 0; kk < 4; kk++) wgmma_ss_n256_t1(o, da + kk * 2, db + kk * 128, 1);
          wgmma_commit();
          if (kb > 0) {
            wgmma_wait<1>();
            release(prevw);
            if (relx >= 0) release(relx);
          }
          prevw = ws;
          prevx = xslot;
        }
        wgmma_wait<0>();
        fence_regs(o);
        release(prevw);
        release(prevx);
        sg.acquire(0);
        store_half_256<0>(o, qs, warp4, lane);
        if (publish) sg.publish(0, lane);
        sg.acquire(1);
        store_half_256<1>(o, qs + 16384, warp4, lane);
        if (publish) sg.publish(1, lane);
      };
      if (!is_main) {
#pragma unroll 1
        for (int item = 0; item < 8; item++) project(true);
      } else
#pragma unroll 1
      for (int item = 0; item < 2; item++) {
        const int j = item == 0 ? 7 - grp : grp;
        project(false);
        fence_async_smem();
        bar_sync(1 + wg, 128);
#pragma unroll
        for (int i = 0; i < 128; i++) o[i] = 0.f;
        fence_regs(o);
        const int tb = 4 * j + b, nskip = 3 - b;
        const int tb_common = 4 * j + bA;
        if (nskip > 0) {
          skip();
          for (int i = 1; i < nskip; i++) { skip(); skip(); }
        }
        const uint32_t dq = desc_kmajor(qs);
        auto issue_qk = [&](int slot) {
          const uint32_t dk = desc_kmajor(sb + slot * 32768);
          wgmma_fence();
          wgmma_ss_n64_t0_z(s, dq, dk);
#pragma unroll
          for (int kk = 1; kk < 16; kk++)
            wgmma_ss_n64_t0(s, dq + (kk >> 2) * 512 + (kk & 3) * 2, dk + (kk >> 2) * 512 + (kk & 3) * 2, 1);
          wgmma_commit();
        };
        auto issue_pv = [&](int slot, uint32_t (&pp)[16]) {
          const uint32_t dv = desc_nmajor128(sb + slot * 32768);
          wgmma_fence();
#pragma unroll
          for (int kk = 0; kk < 4; kk++) wgmma_rs_n256_t1(o, pp[4 * kk], pp[4 * kk + 1], pp[4 * kk + 2], pp[4 * kk + 3], dv + kk * 128, 1);
          wgmma_commit();
        };
        float n0, n1, l0, l1;
        auto numerators = [&](uint32_t (&pp)[16], float& t0, float& t1) {
          t0 = 0.f; t1 = 0.f;
#pragma unroll
          for (int jj = 0; jj < 8; jj++) {
            const float e0 = ex2(fmaf(s[4 * jj], SC, n0)), e1 = ex2(fmaf(s[4 * jj + 1], SC, n0));
            const float e2 = ex2(fmaf(s[4 * jj + 2], SC, n1)), e3 = ex2(fmaf(s[4 * jj + 3], SC, n1));
            t0 += e0 + e1; t1 += e2 + e3;
            pp[2 * jj] = pack_bf16(e0, e1);
            pp[2 * jj + 1] = pack_bf16(e2, e3);
          }
        };
        {
          const int ks = take();
          issue_qk(ks);
          if (nskip > 0) skip();
          wgmma_wait<0>();
          fence_regs(s);
          release(ks);
          const int r0 = warp4 * 16 + (lane >> 2), c0 = (lane & 3) * 2;
#pragma unroll
          for (int jj = 0; jj < 8; jj++) {
            const int c = jj * 8 + c0;
            if (c > r0) s[4 * jj] = -INFINITY;
            if (c + 1 > r0) s[4 * jj + 1] = -INFINITY;
            if (c > r0 + 8) s[4 * jj + 2] = -INFINITY;
            if (c + 1 > r0 + 8) s[4 * jj + 3] = -INFINITY;
          }
          float m0 = -INFINITY, m1 = -INFINITY;
          softmax_rowmax(s, m0, m1);
          n0 = -m0 * SC; n1 = -m1 * SC;
          numerators(pA, l0, l1);
          fence_regs(pA);
        }
        auto step = [&](int t, uint32_t (&pc)[16], uint32_t (&pn)[16]) {
          const bool common = t <= tb_common;
          if (common) bar_sync(3 + wg, 256);
          const int ks = take();
          issue_qk(ks);
          const int vs = take();
          issue_pv(vs, pc);
          if (common) bar_arrive(3 + (wg ^ 1), 256);
          wgmma_wait<1>();
          fence_regs(s);
          release(ks);
          float t0, t1;
          numerators(pn, t0, t1);
          uint32_t mx = __vimax3_u16x2(pn[0], pn[1], pn[2]);
#pragma unroll
          for (int i = 3; i < 15; i += 2) mx = __vimax3_u16x2(mx, pn[i], pn[i + 1]);
          mx = __vimax3_u16x2(mx, pn[15], pn[15]);
          const bool grow = __any_sync(0xffffffffu, max(mx & 0xffffu, mx >> 16) > 0x5380u);
          float a0 = 1.f, a1 = 1.f;
          if (grow) {
            float x0 = -INFINITY, x1 = -INFINITY;
            softmax_rowmax(s, x0, x1);
            const float w0 = fminf(n0, -x0 * SC), w1 = fminf(n1, -x1 * SC);
            a0 = ex2(w0 - n0); a1 = ex2(w1 - n1);
            n0 = w0; n1 = w1;
            l0 *= a0; l1 *= a1;
            numerators(pn, t0, t1);
          }
          l0 += t0; l1 += t1;
          fence_regs(pn);
          wgmma_wait<0>();
          fence_regs(o);
          fence_regs(pc);
          release(vs);
          if (grow) {
#pragma unroll
            for (int i = 0; i < 32; i++) {
              o[4 * i] *= a0; o[4 * i + 1] *= a0; o[4 * i + 2] *= a1; o[4 * i + 3] *= a1;
            }
          }
          fence_regs(o);
        };
        auto last_pv = [&](uint32_t (&pc)[16]) {
          const int vs = take();
          issue_pv(vs, pc);
          wgmma_wait<0>();
          fence_regs(o);
          fence_regs(pc);
          release(vs);
        };
        uint32_t zero;
        asm volatile("mov.u32 %0, 0;" : "=r"(zero));
#pragma unroll 1
        for (int t = tb; t >= 1; t--) {
          step(t, pA, pB);
#pragma unroll
          for (int i = 0; i < 16; i++) asm volatile("xor.b32 %0, %1, %2;" : "=r"(pA[i]) : "r"(pB[i]), "r"(zero));
        }
        last_pv(pA);
        l0 += __shfl_xor_sync(0xffffffffu, l0, 1);
        l1 += __shfl_xor_sync(0xffffffffu, l1, 1);
        l0 += __shfl_xor_sync(0xffffffffu, l0, 2);
        l1 += __shfl_xor_sync(0xffffffffu, l1, 2);
        uint32_t a[64];
        {
          const float i0 = rcp(l0), i1 = rcp(l1);
#pragma unroll
          for (int i = 0; i < 32; i++) {
            a[2 * i] = pack_bf16(o[4 * i] * i0, o[4 * i + 1] * i0);
            a[2 * i + 1] = pack_bf16(o[4 * i + 2] * i1, o[4 * i + 3] * i1);
          }
        }
        fence_regs(a);
        float accA[64], accB[64];
        auto issue128 = [&](float (&acc)[64], int& s0, int& s1) {
          bar_sync(3 + wg, 256);
          s0 = take();
          const uint32_t d0 = (((sb + s0 * 32768) & 0x3FFFFu) >> 4) | (1024u << 16);
          wgmma_fence();
          wgmma_rs_n128_t1_z(acc, a[0], a[1], a[2], a[3], d0);
#pragma unroll
          for (int kk = 1; kk < 8; kk++) wgmma_rs_n128_t1(acc, a[4 * kk], a[4 * kk + 1], a[4 * kk + 2], a[4 * kk + 3], d0 + kk * 128, 1);
          s1 = take();
          const uint32_t d1 = (((sb + s1 * 32768) & 0x3FFFFu) >> 4) | (1024u << 16);
          wgmma_fence();
#pragma unroll
          for (int kk = 8; kk < 16; kk++)
            wgmma_rs_n128_t1(acc, a[4 * kk], a[4 * kk + 1], a[4 * kk + 2], a[4 * kk + 3], d1 + (kk & 7) * 128, 1);
          wgmma_commit();
          bar_arrive(3 + (wg ^ 1), 256);
        };
        auto stage = [&](const float* v, int nb, int bsel) {
          sg.acquire(bsel);
          const int mi = lane >> 3;
          const uint32_t base = qs + bsel * 16384 + (warp4 * 16 + (mi & 1) * 8 + (lane & 7)) * 128;
#pragma unroll
          for (int jj = 0; jj < 16; jj += 2) {
            if (jj < 8 * nb) {
              const uint32_t addr = base + (jj >> 3) * 8192 + ((((jj & 7) + (mi >> 1)) ^ (lane & 7)) << 4);
              stmatrix_x4(addr, pack_bf16(v[4 * jj + 0], v[4 * jj + 1]), pack_bf16(v[4 * jj + 2], v[4 * jj + 3]),
                          pack_bf16(v[4 * jj + 4], v[4 * jj + 5]), pack_bf16(v[4 * jj + 6], v[4 * jj + 7]));
            }
          }
          sg.publish(bsel, lane);
        };
        {
          int s0, s1, s2, s3, s4, s5;
          float (&accC)[32] = *reinterpret_cast<float (*)[32]>(&accB[0]);
          bar_sync(3 + wg, 256);
          const int s6 = take();
          {
            const uint32_t d0 = desc_nmajor128(sb + s6 * 32768);
            wgmma_fence();
            wgmma_rs_n64_t1_z(accC, a[0], a[1], a[2], a[3], d0);
#pragma unroll
            for (int kk = 1; kk < 16; kk++)
              wgmma_rs_n64_t1(accC, a[4 * kk], a[4 * kk + 1], a[4 * kk + 2], a[4 * kk + 3], d0 + kk * 128, 1);
            wgmma_commit();
          }
          bar_arrive(3 + (wg ^ 1), 256);
          issue128(accA, s0, s1);
          wgmma_wait<1>();
          fence_regs(accC);
          release(s6);
          stage(accC, 1, 0);
          issue128(accB, s2, s3);
          wgmma_wait<1>();
          fence_regs(accA);
          release(s0); release(s1);
          stage(accA, 2, 1);
          issue128(accA, s4, s5);
          wgmma_wait<1>();
          fence_regs(accB);
          release(s2); release(s3);
          stage(accB, 2, 0);
          wgmma_wait<0>();
          fence_regs(accA);
          fence_regs(a);
          release(s4); release(s5);
          stage(accA, 2, 1);
        }
      }
    }
  }
  __syncthreads();
  cluster_sync();
  if (tid == 0) {
    if (atomicAdd(&g_flag[F_DONE], 1) == gridDim.x - 1) {
      for (int i = 0; i < F_COUNT; i++) g_flag[i] = 0;
    }
  }
}

typedef CUresult (*EncodeFn)(CUtensorMap*, CUtensorMapDataType, cuuint32_t, void*, const cuuint64_t*, const cuuint64_t*,
                             const cuuint32_t*, const cuuint32_t*, CUtensorMapInterleave, CUtensorMapSwizzle,
                             CUtensorMapL2promotion, CUtensorMapFloatOOBfill);

CUtensorMap make_map2d(EncodeFn enc, const void* p, int rows, int cols, int box_rows) {
  CUtensorMap m;
  cuuint64_t gd[2] = {(cuuint64_t)cols, (cuuint64_t)rows};
  cuuint64_t gs[1] = {(cuuint64_t)cols * 2};
  cuuint32_t bd[2] = {64, (cuuint32_t)box_rows};
  cuuint32_t es[2] = {1, 1};
  enc(&m, CU_TENSOR_MAP_DATA_TYPE_BFLOAT16, 2, const_cast<void*>(p), gd, gs, bd, es, CU_TENSOR_MAP_INTERLEAVE_NONE,
      CU_TENSOR_MAP_SWIZZLE_128B, CU_TENSOR_MAP_L2_PROMOTION_L2_256B, CU_TENSOR_MAP_FLOAT_OOB_FILL_NONE);
  return m;
}
CUtensorMap make_map3d(EncodeFn enc, const void* p, int rows, int cols) {
  CUtensorMap m;
  cuuint64_t gd[3] = {64, (cuuint64_t)rows, (cuuint64_t)(cols / 64)};
  cuuint64_t gs[2] = {(cuuint64_t)cols * 2, 128};
  cuuint32_t bd[3] = {64, 64, 2};
  cuuint32_t es[3] = {1, 1, 1};
  enc(&m, CU_TENSOR_MAP_DATA_TYPE_BFLOAT16, 3, const_cast<void*>(p), gd, gs, bd, es, CU_TENSOR_MAP_INTERLEAVE_NONE,
      CU_TENSOR_MAP_SWIZZLE_128B, CU_TENSOR_MAP_L2_PROMOTION_L2_256B, CU_TENSOR_MAP_FLOAT_OOB_FILL_NONE);
  return m;
}

}

extern "C" void kernel_launch(void* const* d_in, const int* in_sizes, int n_in, void* d_out, int out_size) {
  (void)in_sizes; (void)n_in; (void)out_size;
  static EncodeFn enc = nullptr;
  static void* oA_ptr = nullptr;
  if (!enc) {
    cudaDriverEntryPointQueryResult qr;
    void* fn = nullptr;
    cudaGetDriverEntryPoint("cuTensorMapEncodeTiled", &fn, cudaEnableDefault, &qr);
    enc = (EncodeFn)fn;
    cudaGetSymbolAddress(&oA_ptr, g_oA);
    cudaFuncSetAttribute(mega_kernel, cudaFuncAttributeMaxDynamicSharedMemorySize, MEGA_SMEM);
  }
  const void *A_x = d_in[0], *A_wqkv = d_in[1], *A_wo = d_in[2], *B_x = d_in[3], *B_ckv = d_in[4], *B_wq = d_in[5],
             *B_wuk = d_in[6], *B_wuv = d_in[7], *B_wo = d_in[8];
  __nv_bfloat16* out = (__nv_bfloat16*)d_out;
  Params P;
  P.ax = make_map2d(enc, A_x, SEQ, DM, 128);
  P.wqkv = make_map2d(enc, A_wqkv, DM, 3 * DM, 32);
  P.ckv = make_map2d(enc, B_ckv, SEQ, DC, 128);
  P.wk = make_map3d(enc, B_wuk, DC, 4096);
  P.wv = make_map3d(enc, B_wuv, DC, 4096);
  P.x = make_map2d(enc, B_x, SEQ, DM, 64);
  P.wq = make_map3d(enc, B_wq, DM, 4096);
  P.wo = make_map2d(enc, B_wo, 4096, DM, 128);
  P.oa = make_map2d(enc, oA_ptr, SEQ, DM, 64);
  P.awo = make_map3d(enc, A_wo, DM, DM);
  P.out = make_map2d(enc, out, SEQ, OUTW, 64);
  mega_kernel<<<132, 384, MEGA_SMEM, cudaStreamPerThread>>>(P, out);
}
```
